```python
import torch

def _softmax(x, axis=-1):
    return torch.softmax(x, dim=axis)
def _gelu(x):
    return torch.nn.functional.gelu(x, approximate="tanh")
def _silu(x):
    return torch.nn.functional.silu(x)
def _sigmoid(x):
    return torch.sigmoid(x)
def _layernorm(x, axis=-1, eps=1e-5):
    m = x.mean(dim=axis, keepdim=True)
    v = x.var(dim=axis, keepdim=True, unbiased=False)
    return (x - m) / torch.sqrt(v + eps)
def _scatter_add(tgt, idx, src, axis=0):
    return tgt.clone().index_add_(axis, idx, src)
def _segment_sum(src, seg, n):
    out = torch.zeros((n,) + src.shape[1:], dtype=src.dtype)
    return out.index_add_(0, seg, src)
def _pad(x, pw):
    flat = tuple(v for pair in reversed(pw) for v in pair)
    return torch.nn.functional.pad(x, flat)

kernel_name = 'standalone__gqa_block_cached__near_ridge'

def setup_inputs():

    _w = (lambda a: (lambda t: t.to(torch.bfloat16) if t.is_floating_point() else t)(torch.as_tensor(a)))
    B, Sq, D = 16, 112, 576
    Hq, Hkv, Sk, Dh = 32, 16, 512, 128
    assert Hq % Hkv == 0, (Hq, Hkv)
    return {
        "x": _w((lambda *s: torch.randn(*s, dtype=torch.bfloat16) * 0.8)(B, Sq, D)),
        "k_cache": _w((lambda *s: torch.randn(*s, dtype=torch.bfloat16) * 0.8)(B, Hkv, Sk, Dh)),
        "v_cache": _w((lambda *s: torch.randn(*s, dtype=torch.bfloat16) * 0.05)(B, Hkv, Sk, Dh)),
        "wq": _w((lambda *s: torch.randn(*s, dtype=torch.bfloat16) * 0.8)(D, Hq * Dh) * (D ** -0.5)),
        "wo": _w((lambda *s: torch.randn(*s, dtype=torch.bfloat16) * 0.05)(Hq * Dh, D) * ((Hq * Dh) ** -0.5)),
    }

def reference(x, k_cache, v_cache, wq, wo):
    B, Sq, D = x.shape
    Hq, Dh = 32, 128
    Hkv = k_cache.shape[1]
    rep = Hq // Hkv
    q = (lambda x, *d: x.permute(*d))((x @ wq).reshape(B, Sq, Hq, Dh), 0, 2, 1, 3)
    k = (lambda x, n, axis: torch.repeat_interleave(x, n, dim=axis))(k_cache, rep, axis=1)
    v = (lambda x, n, axis: torch.repeat_interleave(x, n, dim=axis))(v_cache, rep, axis=1)
    scores = torch.einsum("bhqd,bhkd->bhqk", q, k) * (Dh ** -0.5)
    p = _softmax(scores, axis=-1)
    o = torch.einsum("bhqk,bhkd->bhqd", p, v)
    return (lambda x, *d: x.permute(*d))(o, 0, 2, 1, 3).reshape(B, Sq, Hq * Dh) @ wo
```

```cpp
#include <cuda_runtime.h>
#include <cuda_bf16.h>
#include <cuda.h>
#include <stdint.h>
#include <type_traits>

namespace {

constexpr int kB = 16, kSq = 112, kD = 576, kHq = 32, kHkv = 16, kSk = 512, kDh = 128;
constexpr int NSLOT = 7;
constexpr int SLOT = 16384;
constexpr int SUB = kSq * 128;
constexpr int QO = 4 * SUB;
constexpr int RING_OFF = 2 * QO;
constexpr int BAR_OFF = RING_OFF + NSLOT * SLOT;
constexpr int SINK_OFF = BAR_OFF + 512, SINK = 2048;
constexpr int SMEM_BYTES = SINK_OFF + SINK;
constexpr int BAR_FULL = 0, BAR_EMPTY = NSLOT, BAR_XFULL = 2 * NSLOT,
              BAR_XFREE = BAR_XFULL + 8, BAR_STAGE = BAR_XFREE + 1, BAR_DONE = BAR_STAGE + 2, BAR_SINK = BAR_DONE + 1;

__device__ unsigned int g_zero_cnt[kB];

__device__ __forceinline__ void mbar_init(uint32_t bar, uint32_t cnt) {
  asm volatile("mbarrier.init.shared::cta.b64 [%0], %1;" ::"r"(bar), "r"(cnt) : "memory");
}
__device__ __forceinline__ void mbar_expect_tx(uint32_t bar, uint32_t bytes) {
  asm volatile("mbarrier.arrive.expect_tx.shared::cta.b64 _, [%0], %1;" ::"r"(bar), "r"(bytes) : "memory");
}
__device__ __forceinline__ void mbar_arrive(uint32_t bar, uint32_t cnt) {
  asm volatile("mbarrier.arrive.shared::cta.b64 _, [%0], %1;" ::"r"(bar), "r"(cnt) : "memory");
}
__device__ __forceinline__ bool mbar_try(uint32_t bar, uint32_t parity) {
  uint32_t ok;
  asm volatile("{\n.reg .pred p;\nmbarrier.try_wait.parity.shared::cta.b64 p, [%1], %2;\nselp.u32 %0, 1, 0, p;\n}"
               : "=r"(ok) : "r"(bar), "r"(parity) : "memory");
  return ok != 0;
}
__device__ __forceinline__ bool mbar_test(uint32_t bar, uint32_t parity) {
  uint32_t ok;
  asm volatile("{\n.reg .pred p;\nmbarrier.test_wait.parity.shared::cta.b64 p, [%1], %2;\nselp.u32 %0, 1, 0, p;\n}"
               : "=r"(ok) : "r"(bar), "r"(parity) : "memory");
  return ok != 0;
}
__device__ __forceinline__ void mbar_wait(uint32_t bar, uint32_t parity) {
  asm volatile("{\n.reg .pred p;\nWAIT_%=:\nmbarrier.try_wait.parity.shared::cta.b64 p, [%0], %1;\n@p bra DONE_%=;\nbra WAIT_%=;\nDONE_%=:\n}"
               ::"r"(bar), "r"(parity) : "memory");
}
__device__ __forceinline__ void tma2d(uint32_t dst, const CUtensorMap* m, uint32_t bar, int c0, int c1) {
  asm volatile("cp.async.bulk.tensor.2d.shared::cluster.global.mbarrier::complete_tx::bytes [%0], [%1, {%3, %4}], [%2];"
               ::"r"(dst), "l"(m), "r"(bar), "r"(c0), "r"(c1) : "memory");
}
__device__ __forceinline__ void tma3d(uint32_t dst, const CUtensorMap* m, uint32_t bar, int c0, int c1, int c2) {
  asm volatile("cp.async.bulk.tensor.3d.shared::cluster.global.mbarrier::complete_tx::bytes [%0], [%1, {%3, %4, %5}], [%2];"
               ::"r"(dst), "l"(m), "r"(bar), "r"(c0), "r"(c1), "r"(c2) : "memory");
}
__device__ __forceinline__ void tma3d_hint(uint32_t dst, const CUtensorMap* m, uint32_t bar, int c0, int c1, int c2, uint64_t pol) {
  asm volatile("cp.async.bulk.tensor.3d.shared::cluster.global.mbarrier::complete_tx::bytes.L2::cache_hint [%0], [%1, {%3, %4, %5}], [%2], %6;"
               ::"r"(dst), "l"(m), "r"(bar), "r"(c0), "r"(c1), "r"(c2), "l"(pol) : "memory");
}
__device__ __forceinline__ void tma2d_mc(uint32_t dst, const CUtensorMap* m, uint32_t bar, int c0, int c1) {
  asm volatile("cp.async.bulk.tensor.2d.shared::cluster.global.mbarrier::complete_tx::bytes.multicast::cluster [%0], [%1, {%3, %4}], [%2], %5;"
               ::"r"(dst), "l"(m), "r"(bar), "r"(c0), "r"(c1), "h"((uint16_t)3) : "memory");
}
__device__ __forceinline__ void tma3d_mc(uint32_t dst, const CUtensorMap* m, uint32_t bar, int c0, int c1, int c2) {
  asm volatile("cp.async.bulk.tensor.3d.shared::cluster.global.mbarrier::complete_tx::bytes.multicast::cluster [%0], [%1, {%3, %4, %5}], [%2], %6;"
               ::"r"(dst), "l"(m), "r"(bar), "r"(c0), "r"(c1), "r"(c2), "h"((uint16_t)3) : "memory");
}
__device__ __forceinline__ uint32_t mapa(uint32_t a, uint32_t rank) {
  uint32_t r;
  asm("mapa.shared::cluster.u32 %0, %1, %2;" : "=r"(r) : "r"(a), "r"(rank));
  return r;
}
__device__ __forceinline__ void mbar_arrive_cluster(uint32_t bar, uint32_t cnt) {
  asm volatile("mbarrier.arrive.shared::cluster.b64 _, [%0], %1;" ::"r"(bar), "r"(cnt) : "memory");
}
__device__ __forceinline__ void prefetch_map(const CUtensorMap* m) {
  asm volatile("prefetch.tensormap [%0];" ::"l"(m) : "memory");
}
__device__ __forceinline__ void cluster_arrive() { asm volatile("barrier.cluster.arrive.relaxed.aligned;" ::: "memory"); }
__device__ __forceinline__ void cluster_wait() { asm volatile("barrier.cluster.wait.aligned;" ::: "memory"); }
__device__ __forceinline__ uint64_t stream_policy() {
  uint64_t pol;
  asm volatile("createpolicy.fractional.L2::evict_first.b64 %0, 1.0;" : "=l"(pol));
  return pol;
}
__device__ __forceinline__ void l2_prefetch_bulk(const void* p, uint32_t bytes, uint64_t pol) {
  asm volatile("cp.async.bulk.prefetch.L2.global.L2::cache_hint [%0], %1, %2;" ::"l"(p), "r"(bytes), "l"(pol) : "memory");
}
__device__ __forceinline__ void l2_prefetch_line(const void* p) { asm volatile("prefetch.global.L2 [%0];" ::"l"(p) : "memory"); }
__device__ __forceinline__ void bar_sync(int id, int n) { asm volatile("bar.sync %0, %1;" ::"r"(id), "r"(n) : "memory"); }
__device__ __forceinline__ void bar_arrive(int id, int n) { asm volatile("bar.arrive %0, %1;" ::"r"(id), "r"(n) : "memory"); }
__device__ __forceinline__ void wg_fence() { asm volatile("wgmma.fence.sync.aligned;" ::: "memory"); }
__device__ __forceinline__ void wg_commit() { asm volatile("wgmma.commit_group.sync.aligned;" ::: "memory"); }
template <int N> __device__ __forceinline__ void wg_wait() { asm volatile("wgmma.wait_group.sync.aligned %0;" ::"n"(N) : "memory"); }
__device__ __forceinline__ void fence_async_smem() { asm volatile("fence.proxy.async.shared::cta;" ::: "memory"); }
template <int N> __device__ __forceinline__ void pin(float (&r)[N]) {
#pragma unroll
  for (int i = 0; i < N; i++) asm volatile("" : "+f"(r[i])::"memory");
}
template <int N> __device__ __forceinline__ void pin(uint32_t (&r)[N]) {
#pragma unroll
  for (int i = 0; i < N; i++) asm volatile("" : "+r"(r[i])::"memory");
}
template <int N> __device__ __forceinline__ void zero(uint32_t (&r)[N]) {
#pragma unroll
  for (int i = 0; i < N; i++) r[i] = 0;
}
__device__ __forceinline__ float ex2(float x) {
  float y;
  asm("ex2.approx.ftz.f32 %0, %1;" : "=f"(y) : "f"(x));
  return y;
}
__device__ __forceinline__ uint32_t pack2(float lo, float hi) {
  uint32_t r;
  asm("cvt.rn.bf16x2.f32 %0, %1, %2;" : "=r"(r) : "f"(hi), "f"(lo));
  return r;
}
__device__ __forceinline__ void stsm4(uint32_t a, uint32_t r0, uint32_t r1, uint32_t r2, uint32_t r3) {
  asm volatile("stmatrix.sync.aligned.m8n8.x4.shared.b16 [%0], {%1, %2, %3, %4};" ::"r"(a), "r"(r0), "r"(r1), "r"(r2), "r"(r3) : "memory");
}
__device__ __forceinline__ void stsm4t(uint32_t a, uint32_t r0, uint32_t r1, uint32_t r2, uint32_t r3) {
  asm volatile("stmatrix.sync.aligned.m8n8.x4.trans.shared.b16 [%0], {%1, %2, %3, %4};" ::"r"(a), "r"(r0), "r"(r1), "r"(r2), "r"(r3) : "memory");
}
__device__ __forceinline__ uint64_t desc(uint32_t addr, uint32_t lbo, uint32_t hi) {
  uint64_t d;
  asm volatile("mov.b64 %0, {%1, %2};" : "=l"(d) : "r"(((addr & 0x3FFFF) >> 4) | ((lbo >> 4) << 16)), "r"(hi));
  return d;
}

__device__ __forceinline__ void issue_qk(float (&S)[32], uint64_t da, uint64_t db) {
  asm volatile(
      "{\n"
      ".reg .b64 a, b;\n"
      ".reg .pred p0, p1;\n"
      "setp.ne.b32 p0, 0, 0;\n"
      "setp.eq.b32 p1, 0, 0;\n"
      "add.s64 a, %32, 0;\n"
      "add.s64 b, %33, 0;\n"
      "wgmma.mma_async.sync.aligned.m64n64k16.f32.bf16.bf16 {%0, %1, %2, %3, %4, %5, %6, %7, %8, %9, %10, %11, %12, %13, %14, %15, %16, %17, %18, %19, %20, %21, %22, %23, %24, %25, %26, %27, %28, %29, %30, %31}, a, b, p0, 1, 1, 0, 0;\n"
      "add.s64 a, %32, 2;\n"
      "add.s64 b, %33, 2;\n"
      "wgmma.mma_async.sync.aligned.m64n64k16.f32.bf16.bf16 {%0, %1, %2, %3, %4, %5, %6, %7, %8, %9, %10, %11, %12, %13, %14, %15, %16, %17, %18, %19, %20, %21, %22, %23, %24, %25, %26, %27, %28, %29, %30, %31}, a, b, p1, 1, 1, 0, 0;\n"
      "add.s64 a, %32, 4;\n"
      "add.s64 b, %33, 4;\n"
      "wgmma.mma_async.sync.aligned.m64n64k16.f32.bf16.bf16 {%0, %1, %2, %3, %4, %5, %6, %7, %8, %9, %10, %11, %12, %13, %14, %15, %16, %17, %18, %19, %20, %21, %22, %23, %24, %25, %26, %27, %28, %29, %30, %31}, a, b, p1, 1, 1, 0, 0;\n"
      "add.s64 a, %32, 6;\n"
      "add.s64 b, %33, 6;\n"
      "wgmma.mma_async.sync.aligned.m64n64k16.f32.bf16.bf16 {%0, %1, %2, %3, %4, %5, %6, %7, %8, %9, %10, %11, %12, %13, %14, %15, %16, %17, %18, %19, %20, %21, %22, %23, %24, %25, %26, %27, %28, %29, %30, %31}, a, b, p1, 1, 1, 0, 0;\n"
      "add.s64 a, %32, 896;\n"
      "add.s64 b, %33, 512;\n"
      "wgmma.mma_async.sync.aligned.m64n64k16.f32.bf16.bf16 {%0, %1, %2, %3, %4, %5, %6, %7, %8, %9, %10, %11, %12, %13, %14, %15, %16, %17, %18, %19, %20, %21, %22, %23, %24, %25, %26, %27, %28, %29, %30, %31}, a, b, p1, 1, 1, 0, 0;\n"
      "add.s64 a, %32, 898;\n"
      "add.s64 b, %33, 514;\n"
      "wgmma.mma_async.sync.aligned.m64n64k16.f32.bf16.bf16 {%0, %1, %2, %3, %4, %5, %6, %7, %8, %9, %10, %11, %12, %13, %14, %15, %16, %17, %18, %19, %20, %21, %22, %23, %24, %25, %26, %27, %28, %29, %30, %31}, a, b, p1, 1, 1, 0, 0;\n"
      "add.s64 a, %32, 900;\n"
      "add.s64 b, %33, 516;\n"
      "wgmma.mma_async.sync.aligned.m64n64k16.f32.bf16.bf16 {%0, %1, %2, %3, %4, %5, %6, %7, %8, %9, %10, %11, %12, %13, %14, %15, %16, %17, %18, %19, %20, %21, %22, %23, %24, %25, %26, %27, %28, %29, %30, %31}, a, b, p1, 1, 1, 0, 0;\n"
      "add.s64 a, %32, 902;\n"
      "add.s64 b, %33, 518;\n"
      "wgmma.mma_async.sync.aligned.m64n64k16.f32.bf16.bf16 {%0, %1, %2, %3, %4, %5, %6, %7, %8, %9, %10, %11, %12, %13, %14, %15, %16, %17, %18, %19, %20, %21, %22, %23, %24, %25, %26, %27, %28, %29, %30, %31}, a, b, p1, 1, 1, 0, 0;\n"
      "}\n"
      : "=f"(S[0]), "=f"(S[1]), "=f"(S[2]), "=f"(S[3]), "=f"(S[4]), "=f"(S[5]), "=f"(S[6]), "=f"(S[7]),
        "=f"(S[8]), "=f"(S[9]), "=f"(S[10]), "=f"(S[11]), "=f"(S[12]), "=f"(S[13]), "=f"(S[14]), "=f"(S[15]),
        "=f"(S[16]), "=f"(S[17]), "=f"(S[18]), "=f"(S[19]), "=f"(S[20]), "=f"(S[21]), "=f"(S[22]), "=f"(S[23]),
        "=f"(S[24]), "=f"(S[25]), "=f"(S[26]), "=f"(S[27]), "=f"(S[28]), "=f"(S[29]), "=f"(S[30]), "=f"(S[31])
      : "l"(da), "l"(db));
}

__device__ __forceinline__ void issue_pv(float (&O)[64], const uint32_t (&P)[16], uint64_t db, int accumulate) {
  asm volatile(
      "{\n"
      ".reg .b64 b;\n"
      ".reg .pred p0, p1;\n"
      "setp.ne.b32 p0, %81, 0;\n"
      "setp.eq.b32 p1, 0, 0;\n"
      "add.s64 b, %80, 0;\n"
      "wgmma.mma_async.sync.aligned.m64n128k16.f32.bf16.bf16 {%0, %1, %2, %3, %4, %5, %6, %7, %8, %9, %10, %11, %12, %13, %14, %15, %16, %17, %18, %19, %20, %21, %22, %23, %24, %25, %26, %27, %28, %29, %30, %31, %32, %33, %34, %35, %36, %37, %38, %39, %40, %41, %42, %43, %44, %45, %46, %47, %48, %49, %50, %51, %52, %53, %54, %55, %56, %57, %58, %59, %60, %61, %62, %63}, {%64, %65, %66, %67}, b, p0, 1, 1, 1;\n"
      "add.s64 b, %80, 128;\n"
      "wgmma.mma_async.sync.aligned.m64n128k16.f32.bf16.bf16 {%0, %1, %2, %3, %4, %5, %6, %7, %8, %9, %10, %11, %12, %13, %14, %15, %16, %17, %18, %19, %20, %21, %22, %23, %24, %25, %26, %27, %28, %29, %30, %31, %32, %33, %34, %35, %36, %37, %38, %39, %40, %41, %42, %43, %44, %45, %46, %47, %48, %49, %50, %51, %52, %53, %54, %55, %56, %57, %58, %59, %60, %61, %62, %63}, {%68, %69, %70, %71}, b, p1, 1, 1, 1;\n"
      "add.s64 b, %80, 256;\n"
      "wgmma.mma_async.sync.aligned.m64n128k16.f32.bf16.bf16 {%0, %1, %2, %3, %4, %5, %6, %7, %8, %9, %10, %11, %12, %13, %14, %15, %16, %17, %18, %19, %20, %21, %22, %23, %24, %25, %26, %27, %28, %29, %30, %31, %32, %33, %34, %35, %36, %37, %38, %39, %40, %41, %42, %43, %44, %45, %46, %47, %48, %49, %50, %51, %52, %53, %54, %55, %56, %57, %58, %59, %60, %61, %62, %63}, {%72, %73, %74, %75}, b, p1, 1, 1, 1;\n"
      "add.s64 b, %80, 384;\n"
      "wgmma.mma_async.sync.aligned.m64n128k16.f32.bf16.bf16 {%0, %1, %2, %3, %4, %5, %6, %7, %8, %9, %10, %11, %12, %13, %14, %15, %16, %17, %18, %19, %20, %21, %22, %23, %24, %25, %26, %27, %28, %29, %30, %31, %32, %33, %34, %35, %36, %37, %38, %39, %40, %41, %42, %43, %44, %45, %46, %47, %48, %49, %50, %51, %52, %53, %54, %55, %56, %57, %58, %59, %60, %61, %62, %63}, {%76, %77, %78, %79}, b, p1, 1, 1, 1;\n"
      "}\n"
      : "+f"(O[0]), "+f"(O[1]), "+f"(O[2]), "+f"(O[3]), "+f"(O[4]), "+f"(O[5]), "+f"(O[6]), "+f"(O[7]),
        "+f"(O[8]), "+f"(O[9]), "+f"(O[10]), "+f"(O[11]), "+f"(O[12]), "+f"(O[13]), "+f"(O[14]), "+f"(O[15]),
        "+f"(O[16]), "+f"(O[17]), "+f"(O[18]), "+f"(O[19]), "+f"(O[20]), "+f"(O[21]), "+f"(O[22]), "+f"(O[23]),
        "+f"(O[24]), "+f"(O[25]), "+f"(O[26]), "+f"(O[27]), "+f"(O[28]), "+f"(O[29]), "+f"(O[30]), "+f"(O[31]),
        "+f"(O[32]), "+f"(O[33]), "+f"(O[34]), "+f"(O[35]), "+f"(O[36]), "+f"(O[37]), "+f"(O[38]), "+f"(O[39]),
        "+f"(O[40]), "+f"(O[41]), "+f"(O[42]), "+f"(O[43]), "+f"(O[44]), "+f"(O[45]), "+f"(O[46]), "+f"(O[47]),
        "+f"(O[48]), "+f"(O[49]), "+f"(O[50]), "+f"(O[51]), "+f"(O[52]), "+f"(O[53]), "+f"(O[54]), "+f"(O[55]),
        "+f"(O[56]), "+f"(O[57]), "+f"(O[58]), "+f"(O[59]), "+f"(O[60]), "+f"(O[61]), "+f"(O[62]), "+f"(O[63])
      : "r"(P[0]), "r"(P[1]), "r"(P[2]), "r"(P[3]), "r"(P[4]), "r"(P[5]), "r"(P[6]), "r"(P[7]), "r"(P[8]), "r"(P[9]), "r"(P[10]), "r"(P[11]), "r"(P[12]), "r"(P[13]), "r"(P[14]), "r"(P[15]), "l"(db), "r"(accumulate));
}

__device__ __forceinline__ void issue_qproj(float (&A0)[56], float (&A1)[56], uint64_t da, uint64_t db) {
  asm volatile(
      "{\n"
      ".reg .b64 a, b;\n"
      ".reg .pred p0, p1;\n"
      "setp.ne.b32 p0, 0, 0;\n"
      "setp.eq.b32 p1, 0, 0;\n"
      "add.s64 a, %112, 0;\n"
      "add.s64 b, %113, 0;\n"
      "wgmma.mma_async.sync.aligned.m64n112k16.f32.bf16.bf16 {%0, %1, %2, %3, %4, %5, %6, %7, %8, %9, %10, %11, %12, %13, %14, %15, %16, %17, %18, %19, %20, %21, %22, %23, %24, %25, %26, %27, %28, %29, %30, %31, %32, %33, %34, %35, %36, %37, %38, %39, %40, %41, %42, %43, %44, %45, %46, %47, %48, %49, %50, %51, %52, %53, %54, %55}, a, b, p1, 1, 1, 1, 0;\n"
      "add.s64 a, %112, 512;\n"
      "add.s64 b, %113, 0;\n"
      "wgmma.mma_async.sync.aligned.m64n112k16.f32.bf16.bf16 {%56, %57, %58, %59, %60, %61, %62, %63, %64, %65, %66, %67, %68, %69, %70, %71, %72, %73, %74, %75, %76, %77, %78, %79, %80, %81, %82, %83, %84, %85, %86, %87, %88, %89, %90, %91, %92, %93, %94, %95, %96, %97, %98, %99, %100, %101, %102, %103, %104, %105, %106, %107, %108, %109, %110, %111}, a, b, p1, 1, 1, 1, 0;\n"
      "add.s64 a, %112, 128;\n"
      "add.s64 b, %113, 2;\n"
      "wgmma.mma_async.sync.aligned.m64n112k16.f32.bf16.bf16 {%0, %1, %2, %3, %4, %5, %6, %7, %8, %9, %10, %11, %12, %13, %14, %15, %16, %17, %18, %19, %20, %21, %22, %23, %24, %25, %26, %27, %28, %29, %30, %31, %32, %33, %34, %35, %36, %37, %38, %39, %40, %41, %42, %43, %44, %45, %46, %47, %48, %49, %50, %51, %52, %53, %54, %55}, a, b, p1, 1, 1, 1, 0;\n"
      "add.s64 a, %112, 640;\n"
      "add.s64 b, %113, 2;\n"
      "wgmma.mma_async.sync.aligned.m64n112k16.f32.bf16.bf16 {%56, %57, %58, %59, %60, %61, %62, %63, %64, %65, %66, %67, %68, %69, %70, %71, %72, %73, %74, %75, %76, %77, %78, %79, %80, %81, %82, %83, %84, %85, %86, %87, %88, %89, %90, %91, %92, %93, %94, %95, %96, %97, %98, %99, %100, %101, %102, %103, %104, %105, %106, %107, %108, %109, %110, %111}, a, b, p1, 1, 1, 1, 0;\n"
      "add.s64 a, %112, 256;\n"
      "add.s64 b, %113, 4;\n"
      "wgmma.mma_async.sync.aligned.m64n112k16.f32.bf16.bf16 {%0, %1, %2, %3, %4, %5, %6, %7, %8, %9, %10, %11, %12, %13, %14, %15, %16, %17, %18, %19, %20, %21, %22, %23, %24, %25, %26, %27, %28, %29, %30, %31, %32, %33, %34, %35, %36, %37, %38, %39, %40, %41, %42, %43, %44, %45, %46, %47, %48, %49, %50, %51, %52, %53, %54, %55}, a, b, p1, 1, 1, 1, 0;\n"
      "add.s64 a, %112, 768;\n"
      "add.s64 b, %113, 4;\n"
      "wgmma.mma_async.sync.aligned.m64n112k16.f32.bf16.bf16 {%56, %57, %58, %59, %60, %61, %62, %63, %64, %65, %66, %67, %68, %69, %70, %71, %72, %73, %74, %75, %76, %77, %78, %79, %80, %81, %82, %83, %84, %85, %86, %87, %88, %89, %90, %91, %92, %93, %94, %95, %96, %97, %98, %99, %100, %101, %102, %103, %104, %105, %106, %107, %108, %109, %110, %111}, a, b, p1, 1, 1, 1, 0;\n"
      "add.s64 a, %112, 384;\n"
      "add.s64 b, %113, 6;\n"
      "wgmma.mma_async.sync.aligned.m64n112k16.f32.bf16.bf16 {%0, %1, %2, %3, %4, %5, %6, %7, %8, %9, %10, %11, %12, %13, %14, %15, %16, %17, %18, %19, %20, %21, %22, %23, %24, %25, %26, %27, %28, %29, %30, %31, %32, %33, %34, %35, %36, %37, %38, %39, %40, %41, %42, %43, %44, %45, %46, %47, %48, %49, %50, %51, %52, %53, %54, %55}, a, b, p1, 1, 1, 1, 0;\n"
      "add.s64 a, %112, 896;\n"
      "add.s64 b, %113, 6;\n"
      "wgmma.mma_async.sync.aligned.m64n112k16.f32.bf16.bf16 {%56, %57, %58, %59, %60, %61, %62, %63, %64, %65, %66, %67, %68, %69, %70, %71, %72, %73, %74, %75, %76, %77, %78, %79, %80, %81, %82, %83, %84, %85, %86, %87, %88, %89, %90, %91, %92, %93, %94, %95, %96, %97, %98, %99, %100, %101, %102, %103, %104, %105, %106, %107, %108, %109, %110, %111}, a, b, p1, 1, 1, 1, 0;\n"
      "}\n"
      : "+f"(A0[0]), "+f"(A0[1]), "+f"(A0[2]), "+f"(A0[3]), "+f"(A0[4]), "+f"(A0[5]), "+f"(A0[6]), "+f"(A0[7]),
        "+f"(A0[8]), "+f"(A0[9]), "+f"(A0[10]), "+f"(A0[11]), "+f"(A0[12]), "+f"(A0[13]), "+f"(A0[14]), "+f"(A0[15]),
        "+f"(A0[16]), "+f"(A0[17]), "+f"(A0[18]), "+f"(A0[19]), "+f"(A0[20]), "+f"(A0[21]), "+f"(A0[22]), "+f"(A0[23]),
        "+f"(A0[24]), "+f"(A0[25]), "+f"(A0[26]), "+f"(A0[27]), "+f"(A0[28]), "+f"(A0[29]), "+f"(A0[30]), "+f"(A0[31]),
        "+f"(A0[32]), "+f"(A0[33]), "+f"(A0[34]), "+f"(A0[35]), "+f"(A0[36]), "+f"(A0[37]), "+f"(A0[38]), "+f"(A0[39]),
        "+f"(A0[40]), "+f"(A0[41]), "+f"(A0[42]), "+f"(A0[43]), "+f"(A0[44]), "+f"(A0[45]), "+f"(A0[46]), "+f"(A0[47]),
        "+f"(A0[48]), "+f"(A0[49]), "+f"(A0[50]), "+f"(A0[51]), "+f"(A0[52]), "+f"(A0[53]), "+f"(A0[54]), "+f"(A0[55]),
        "+f"(A1[0]), "+f"(A1[1]), "+f"(A1[2]), "+f"(A1[3]), "+f"(A1[4]), "+f"(A1[5]), "+f"(A1[6]), "+f"(A1[7]),
        "+f"(A1[8]), "+f"(A1[9]), "+f"(A1[10]), "+f"(A1[11]), "+f"(A1[12]), "+f"(A1[13]), "+f"(A1[14]), "+f"(A1[15]),
        "+f"(A1[16]), "+f"(A1[17]), "+f"(A1[18]), "+f"(A1[19]), "+f"(A1[20]), "+f"(A1[21]), "+f"(A1[22]), "+f"(A1[23]),
        "+f"(A1[24]), "+f"(A1[25]), "+f"(A1[26]), "+f"(A1[27]), "+f"(A1[28]), "+f"(A1[29]), "+f"(A1[30]), "+f"(A1[31]),
        "+f"(A1[32]), "+f"(A1[33]), "+f"(A1[34]), "+f"(A1[35]), "+f"(A1[36]), "+f"(A1[37]), "+f"(A1[38]), "+f"(A1[39]),
        "+f"(A1[40]), "+f"(A1[41]), "+f"(A1[42]), "+f"(A1[43]), "+f"(A1[44]), "+f"(A1[45]), "+f"(A1[46]), "+f"(A1[47]),
        "+f"(A1[48]), "+f"(A1[49]), "+f"(A1[50]), "+f"(A1[51]), "+f"(A1[52]), "+f"(A1[53]), "+f"(A1[54]), "+f"(A1[55])
      : "l"(da), "l"(db));
}

__device__ __forceinline__ void issue_qproj_first(float (&A0)[56], float (&A1)[56], uint64_t da, uint64_t db) {
  asm volatile(
      "{\n"
      ".reg .b64 a, b;\n"
      ".reg .pred p0, p1;\n"
      "setp.ne.b32 p0, 0, 0;\n"
      "setp.eq.b32 p1, 0, 0;\n"
      "add.s64 a, %112, 0;\n"
      "add.s64 b, %113, 0;\n"
      "wgmma.mma_async.sync.aligned.m64n112k16.f32.bf16.bf16 {%0, %1, %2, %3, %4, %5, %6, %7, %8, %9, %10, %11, %12, %13, %14, %15, %16, %17, %18, %19, %20, %21, %22, %23, %24, %25, %26, %27, %28, %29, %30, %31, %32, %33, %34, %35, %36, %37, %38, %39, %40, %41, %42, %43, %44, %45, %46, %47, %48, %49, %50, %51, %52, %53, %54, %55}, a, b, p0, 1, 1, 1, 0;\n"
      "add.s64 a, %112, 512;\n"
      "add.s64 b, %113, 0;\n"
      "wgmma.mma_async.sync.aligned.m64n112k16.f32.bf16.bf16 {%56, %57, %58, %59, %60, %61, %62, %63, %64, %65, %66, %67, %68, %69, %70, %71, %72, %73, %74, %75, %76, %77, %78, %79, %80, %81, %82, %83, %84, %85, %86, %87, %88, %89, %90, %91, %92, %93, %94, %95, %96, %97, %98, %99, %100, %101, %102, %103, %104, %105, %106, %107, %108, %109, %110, %111}, a, b, p0, 1, 1, 1, 0;\n"
      "add.s64 a, %112, 128;\n"
      "add.s64 b, %113, 2;\n"
      "wgmma.mma_async.sync.aligned.m64n112k16.f32.bf16.bf16 {%0, %1, %2, %3, %4, %5, %6, %7, %8, %9, %10, %11, %12, %13, %14, %15, %16, %17, %18, %19, %20, %21, %22, %23, %24, %25, %26, %27, %28, %29, %30, %31, %32, %33, %34, %35, %36, %37, %38, %39, %40, %41, %42, %43, %44, %45, %46, %47, %48, %49, %50, %51, %52, %53, %54, %55}, a, b, p1, 1, 1, 1, 0;\n"
      "add.s64 a, %112, 640;\n"
      "add.s64 b, %113, 2;\n"
      "wgmma.mma_async.sync.aligned.m64n112k16.f32.bf16.bf16 {%56, %57, %58, %59, %60, %61, %62, %63, %64, %65, %66, %67, %68, %69, %70, %71, %72, %73, %74, %75, %76, %77, %78, %79, %80, %81, %82, %83, %84, %85, %86, %87, %88, %89, %90, %91, %92, %93, %94, %95, %96, %97, %98, %99, %100, %101, %102, %103, %104, %105, %106, %107, %108, %109, %110, %111}, a, b, p1, 1, 1, 1, 0;\n"
      "add.s64 a, %112, 256;\n"
      "add.s64 b, %113, 4;\n"
      "wgmma.mma_async.sync.aligned.m64n112k16.f32.bf16.bf16 {%0, %1, %2, %3, %4, %5, %6, %7, %8, %9, %10, %11, %12, %13, %14, %15, %16, %17, %18, %19, %20, %21, %22, %23, %24, %25, %26, %27, %28, %29, %30, %31, %32, %33, %34, %35, %36, %37, %38, %39, %40, %41, %42, %43, %44, %45, %46, %47, %48, %49, %50, %51, %52, %53, %54, %55}, a, b, p1, 1, 1, 1, 0;\n"
      "add.s64 a, %112, 768;\n"
      "add.s64 b, %113, 4;\n"
      "wgmma.mma_async.sync.aligned.m64n112k16.f32.bf16.bf16 {%56, %57, %58, %59, %60, %61, %62, %63, %64, %65, %66, %67, %68, %69, %70, %71, %72, %73, %74, %75, %76, %77, %78, %79, %80, %81, %82, %83, %84, %85, %86, %87, %88, %89, %90, %91, %92, %93, %94, %95, %96, %97, %98, %99, %100, %101, %102, %103, %104, %105, %106, %107, %108, %109, %110, %111}, a, b, p1, 1, 1, 1, 0;\n"
      "add.s64 a, %112, 384;\n"
      "add.s64 b, %113, 6;\n"
      "wgmma.mma_async.sync.aligned.m64n112k16.f32.bf16.bf16 {%0, %1, %2, %3, %4, %5, %6, %7, %8, %9, %10, %11, %12, %13, %14, %15, %16, %17, %18, %19, %20, %21, %22, %23, %24, %25, %26, %27, %28, %29, %30, %31, %32, %33, %34, %35, %36, %37, %38, %39, %40, %41, %42, %43, %44, %45, %46, %47, %48, %49, %50, %51, %52, %53, %54, %55}, a, b, p1, 1, 1, 1, 0;\n"
      "add.s64 a, %112, 896;\n"
      "add.s64 b, %113, 6;\n"
      "wgmma.mma_async.sync.aligned.m64n112k16.f32.bf16.bf16 {%56, %57, %58, %59, %60, %61, %62, %63, %64, %65, %66, %67, %68, %69, %70, %71, %72, %73, %74, %75, %76, %77, %78, %79, %80, %81, %82, %83, %84, %85, %86, %87, %88, %89, %90, %91, %92, %93, %94, %95, %96, %97, %98, %99, %100, %101, %102, %103, %104, %105, %106, %107, %108, %109, %110, %111}, a, b, p1, 1, 1, 1, 0;\n"
      "}\n"
      : "=f"(A0[0]), "=f"(A0[1]), "=f"(A0[2]), "=f"(A0[3]), "=f"(A0[4]), "=f"(A0[5]), "=f"(A0[6]), "=f"(A0[7]),
        "=f"(A0[8]), "=f"(A0[9]), "=f"(A0[10]), "=f"(A0[11]), "=f"(A0[12]), "=f"(A0[13]), "=f"(A0[14]), "=f"(A0[15]),
        "=f"(A0[16]), "=f"(A0[17]), "=f"(A0[18]), "=f"(A0[19]), "=f"(A0[20]), "=f"(A0[21]), "=f"(A0[22]), "=f"(A0[23]),
        "=f"(A0[24]), "=f"(A0[25]), "=f"(A0[26]), "=f"(A0[27]), "=f"(A0[28]), "=f"(A0[29]), "=f"(A0[30]), "=f"(A0[31]),
        "=f"(A0[32]), "=f"(A0[33]), "=f"(A0[34]), "=f"(A0[35]), "=f"(A0[36]), "=f"(A0[37]), "=f"(A0[38]), "=f"(A0[39]),
        "=f"(A0[40]), "=f"(A0[41]), "=f"(A0[42]), "=f"(A0[43]), "=f"(A0[44]), "=f"(A0[45]), "=f"(A0[46]), "=f"(A0[47]),
        "=f"(A0[48]), "=f"(A0[49]), "=f"(A0[50]), "=f"(A0[51]), "=f"(A0[52]), "=f"(A0[53]), "=f"(A0[54]), "=f"(A0[55]),
        "=f"(A1[0]), "=f"(A1[1]), "=f"(A1[2]), "=f"(A1[3]), "=f"(A1[4]), "=f"(A1[5]), "=f"(A1[6]), "=f"(A1[7]),
        "=f"(A1[8]), "=f"(A1[9]), "=f"(A1[10]), "=f"(A1[11]), "=f"(A1[12]), "=f"(A1[13]), "=f"(A1[14]), "=f"(A1[15]),
        "=f"(A1[16]), "=f"(A1[17]), "=f"(A1[18]), "=f"(A1[19]), "=f"(A1[20]), "=f"(A1[21]), "=f"(A1[22]), "=f"(A1[23]),
        "=f"(A1[24]), "=f"(A1[25]), "=f"(A1[26]), "=f"(A1[27]), "=f"(A1[28]), "=f"(A1[29]), "=f"(A1[30]), "=f"(A1[31]),
        "=f"(A1[32]), "=f"(A1[33]), "=f"(A1[34]), "=f"(A1[35]), "=f"(A1[36]), "=f"(A1[37]), "=f"(A1[38]), "=f"(A1[39]),
        "=f"(A1[40]), "=f"(A1[41]), "=f"(A1[42]), "=f"(A1[43]), "=f"(A1[44]), "=f"(A1[45]), "=f"(A1[46]), "=f"(A1[47]),
        "=f"(A1[48]), "=f"(A1[49]), "=f"(A1[50]), "=f"(A1[51]), "=f"(A1[52]), "=f"(A1[53]), "=f"(A1[54]), "=f"(A1[55])
      : "l"(da), "l"(db));
}

__device__ __forceinline__ void issue_qproj_acc(float (&A0)[56], float (&A1)[56], uint64_t da, uint64_t db, int accumulate) {
  asm volatile(
      "{\n"
      ".reg .b64 a, b;\n"
      ".reg .pred p0, p1;\n"
      "setp.ne.b32 p0, %114, 0;\n"
      "setp.eq.b32 p1, 0, 0;\n"
      "add.s64 a, %112, 0;\n"
      "add.s64 b, %113, 0;\n"
      "wgmma.mma_async.sync.aligned.m64n112k16.f32.bf16.bf16 {%0, %1, %2, %3, %4, %5, %6, %7, %8, %9, %10, %11, %12, %13, %14, %15, %16, %17, %18, %19, %20, %21, %22, %23, %24, %25, %26, %27, %28, %29, %30, %31, %32, %33, %34, %35, %36, %37, %38, %39, %40, %41, %42, %43, %44, %45, %46, %47, %48, %49, %50, %51, %52, %53, %54, %55}, a, b, p0, 1, 1, 1, 0;\n"
      "add.s64 a, %112, 512;\n"
      "add.s64 b, %113, 0;\n"
      "wgmma.mma_async.sync.aligned.m64n112k16.f32.bf16.bf16 {%56, %57, %58, %59, %60, %61, %62, %63, %64, %65, %66, %67, %68, %69, %70, %71, %72, %73, %74, %75, %76, %77, %78, %79, %80, %81, %82, %83, %84, %85, %86, %87, %88, %89, %90, %91, %92, %93, %94, %95, %96, %97, %98, %99, %100, %101, %102, %103, %104, %105, %106, %107, %108, %109, %110, %111}, a, b, p0, 1, 1, 1, 0;\n"
      "add.s64 a, %112, 128;\n"
      "add.s64 b, %113, 2;\n"
      "wgmma.mma_async.sync.aligned.m64n112k16.f32.bf16.bf16 {%0, %1, %2, %3, %4, %5, %6, %7, %8, %9, %10, %11, %12, %13, %14, %15, %16, %17, %18, %19, %20, %21, %22, %23, %24, %25, %26, %27, %28, %29, %30, %31, %32, %33, %34, %35, %36, %37, %38, %39, %40, %41, %42, %43, %44, %45, %46, %47, %48, %49, %50, %51, %52, %53, %54, %55}, a, b, p1, 1, 1, 1, 0;\n"
      "add.s64 a, %112, 640;\n"
      "add.s64 b, %113, 2;\n"
      "wgmma.mma_async.sync.aligned.m64n112k16.f32.bf16.bf16 {%56, %57, %58, %59, %60, %61, %62, %63, %64, %65, %66, %67, %68, %69, %70, %71, %72, %73, %74, %75, %76, %77, %78, %79, %80, %81, %82, %83, %84, %85, %86, %87, %88, %89, %90, %91, %92, %93, %94, %95, %96, %97, %98, %99, %100, %101, %102, %103, %104, %105, %106, %107, %108, %109, %110, %111}, a, b, p1, 1, 1, 1, 0;\n"
      "add.s64 a, %112, 256;\n"
      "add.s64 b, %113, 4;\n"
      "wgmma.mma_async.sync.aligned.m64n112k16.f32.bf16.bf16 {%0, %1, %2, %3, %4, %5, %6, %7, %8, %9, %10, %11, %12, %13, %14, %15, %16, %17, %18, %19, %20, %21, %22, %23, %24, %25, %26, %27, %28, %29, %30, %31, %32, %33, %34, %35, %36, %37, %38, %39, %40, %41, %42, %43, %44, %45, %46, %47, %48, %49, %50, %51, %52, %53, %54, %55}, a, b, p1, 1, 1, 1, 0;\n"
      "add.s64 a, %112, 768;\n"
      "add.s64 b, %113, 4;\n"
      "wgmma.mma_async.sync.aligned.m64n112k16.f32.bf16.bf16 {%56, %57, %58, %59, %60, %61, %62, %63, %64, %65, %66, %67, %68, %69, %70, %71, %72, %73, %74, %75, %76, %77, %78, %79, %80, %81, %82, %83, %84, %85, %86, %87, %88, %89, %90, %91, %92, %93, %94, %95, %96, %97, %98, %99, %100, %101, %102, %103, %104, %105, %106, %107, %108, %109, %110, %111}, a, b, p1, 1, 1, 1, 0;\n"
      "add.s64 a, %112, 384;\n"
      "add.s64 b, %113, 6;\n"
      "wgmma.mma_async.sync.aligned.m64n112k16.f32.bf16.bf16 {%0, %1, %2, %3, %4, %5, %6, %7, %8, %9, %10, %11, %12, %13, %14, %15, %16, %17, %18, %19, %20, %21, %22, %23, %24, %25, %26, %27, %28, %29, %30, %31, %32, %33, %34, %35, %36, %37, %38, %39, %40, %41, %42, %43, %44, %45, %46, %47, %48, %49, %50, %51, %52, %53, %54, %55}, a, b, p1, 1, 1, 1, 0;\n"
      "add.s64 a, %112, 896;\n"
      "add.s64 b, %113, 6;\n"
      "wgmma.mma_async.sync.aligned.m64n112k16.f32.bf16.bf16 {%56, %57, %58, %59, %60, %61, %62, %63, %64, %65, %66, %67, %68, %69, %70, %71, %72, %73, %74, %75, %76, %77, %78, %79, %80, %81, %82, %83, %84, %85, %86, %87, %88, %89, %90, %91, %92, %93, %94, %95, %96, %97, %98, %99, %100, %101, %102, %103, %104, %105, %106, %107, %108, %109, %110, %111}, a, b, p1, 1, 1, 1, 0;\n"
      "}\n"
      : "+f"(A0[0]), "+f"(A0[1]), "+f"(A0[2]), "+f"(A0[3]), "+f"(A0[4]), "+f"(A0[5]), "+f"(A0[6]), "+f"(A0[7]),
        "+f"(A0[8]), "+f"(A0[9]), "+f"(A0[10]), "+f"(A0[11]), "+f"(A0[12]), "+f"(A0[13]), "+f"(A0[14]), "+f"(A0[15]),
        "+f"(A0[16]), "+f"(A0[17]), "+f"(A0[18]), "+f"(A0[19]), "+f"(A0[20]), "+f"(A0[21]), "+f"(A0[22]), "+f"(A0[23]),
        "+f"(A0[24]), "+f"(A0[25]), "+f"(A0[26]), "+f"(A0[27]), "+f"(A0[28]), "+f"(A0[29]), "+f"(A0[30]), "+f"(A0[31]),
        "+f"(A0[32]), "+f"(A0[33]), "+f"(A0[34]), "+f"(A0[35]), "+f"(A0[36]), "+f"(A0[37]), "+f"(A0[38]), "+f"(A0[39]),
        "+f"(A0[40]), "+f"(A0[41]), "+f"(A0[42]), "+f"(A0[43]), "+f"(A0[44]), "+f"(A0[45]), "+f"(A0[46]), "+f"(A0[47]),
        "+f"(A0[48]), "+f"(A0[49]), "+f"(A0[50]), "+f"(A0[51]), "+f"(A0[52]), "+f"(A0[53]), "+f"(A0[54]), "+f"(A0[55]),
        "+f"(A1[0]), "+f"(A1[1]), "+f"(A1[2]), "+f"(A1[3]), "+f"(A1[4]), "+f"(A1[5]), "+f"(A1[6]), "+f"(A1[7]),
        "+f"(A1[8]), "+f"(A1[9]), "+f"(A1[10]), "+f"(A1[11]), "+f"(A1[12]), "+f"(A1[13]), "+f"(A1[14]), "+f"(A1[15]),
        "+f"(A1[16]), "+f"(A1[17]), "+f"(A1[18]), "+f"(A1[19]), "+f"(A1[20]), "+f"(A1[21]), "+f"(A1[22]), "+f"(A1[23]),
        "+f"(A1[24]), "+f"(A1[25]), "+f"(A1[26]), "+f"(A1[27]), "+f"(A1[28]), "+f"(A1[29]), "+f"(A1[30]), "+f"(A1[31]),
        "+f"(A1[32]), "+f"(A1[33]), "+f"(A1[34]), "+f"(A1[35]), "+f"(A1[36]), "+f"(A1[37]), "+f"(A1[38]), "+f"(A1[39]),
        "+f"(A1[40]), "+f"(A1[41]), "+f"(A1[42]), "+f"(A1[43]), "+f"(A1[44]), "+f"(A1[45]), "+f"(A1[46]), "+f"(A1[47]),
        "+f"(A1[48]), "+f"(A1[49]), "+f"(A1[50]), "+f"(A1[51]), "+f"(A1[52]), "+f"(A1[53]), "+f"(A1[54]), "+f"(A1[55])
      : "l"(da), "l"(db), "r"(accumulate));
}

__device__ __forceinline__ void issue_oproj_first(float (&A)[56], uint64_t da, uint64_t db) {
  asm volatile(
      "{\n"
      ".reg .b64 a, b;\n"
      ".reg .pred p0, p1;\n"
      "setp.ne.b32 p0, 0, 0;\n"
      "setp.eq.b32 p1, 0, 0;\n"
      "add.s64 a, %56, 0;\n"
      "add.s64 b, %57, 0;\n"
      "wgmma.mma_async.sync.aligned.m64n112k16.f32.bf16.bf16 {%0, %1, %2, %3, %4, %5, %6, %7, %8, %9, %10, %11, %12, %13, %14, %15, %16, %17, %18, %19, %20, %21, %22, %23, %24, %25, %26, %27, %28, %29, %30, %31, %32, %33, %34, %35, %36, %37, %38, %39, %40, %41, %42, %43, %44, %45, %46, %47, %48, %49, %50, %51, %52, %53, %54, %55}, a, b, p0, 1, 1, 1, 0;\n"
      "add.s64 a, %56, 128;\n"
      "add.s64 b, %57, 2;\n"
      "wgmma.mma_async.sync.aligned.m64n112k16.f32.bf16.bf16 {%0, %1, %2, %3, %4, %5, %6, %7, %8, %9, %10, %11, %12, %13, %14, %15, %16, %17, %18, %19, %20, %21, %22, %23, %24, %25, %26, %27, %28, %29, %30, %31, %32, %33, %34, %35, %36, %37, %38, %39, %40, %41, %42, %43, %44, %45, %46, %47, %48, %49, %50, %51, %52, %53, %54, %55}, a, b, p1, 1, 1, 1, 0;\n"
      "add.s64 a, %56, 256;\n"
      "add.s64 b, %57, 4;\n"
      "wgmma.mma_async.sync.aligned.m64n112k16.f32.bf16.bf16 {%0, %1, %2, %3, %4, %5, %6, %7, %8, %9, %10, %11, %12, %13, %14, %15, %16, %17, %18, %19, %20, %21, %22, %23, %24, %25, %26, %27, %28, %29, %30, %31, %32, %33, %34, %35, %36, %37, %38, %39, %40, %41, %42, %43, %44, %45, %46, %47, %48, %49, %50, %51, %52, %53, %54, %55}, a, b, p1, 1, 1, 1, 0;\n"
      "add.s64 a, %56, 384;\n"
      "add.s64 b, %57, 6;\n"
      "wgmma.mma_async.sync.aligned.m64n112k16.f32.bf16.bf16 {%0, %1, %2, %3, %4, %5, %6, %7, %8, %9, %10, %11, %12, %13, %14, %15, %16, %17, %18, %19, %20, %21, %22, %23, %24, %25, %26, %27, %28, %29, %30, %31, %32, %33, %34, %35, %36, %37, %38, %39, %40, %41, %42, %43, %44, %45, %46, %47, %48, %49, %50, %51, %52, %53, %54, %55}, a, b, p1, 1, 1, 1, 0;\n"
      "add.s64 a, %56, 512;\n"
      "add.s64 b, %57, 896;\n"
      "wgmma.mma_async.sync.aligned.m64n112k16.f32.bf16.bf16 {%0, %1, %2, %3, %4, %5, %6, %7, %8, %9, %10, %11, %12, %13, %14, %15, %16, %17, %18, %19, %20, %21, %22, %23, %24, %25, %26, %27, %28, %29, %30, %31, %32, %33, %34, %35, %36, %37, %38, %39, %40, %41, %42, %43, %44, %45, %46, %47, %48, %49, %50, %51, %52, %53, %54, %55}, a, b, p1, 1, 1, 1, 0;\n"
      "add.s64 a, %56, 640;\n"
      "add.s64 b, %57, 898;\n"
      "wgmma.mma_async.sync.aligned.m64n112k16.f32.bf16.bf16 {%0, %1, %2, %3, %4, %5, %6, %7, %8, %9, %10, %11, %12, %13, %14, %15, %16, %17, %18, %19, %20, %21, %22, %23, %24, %25, %26, %27, %28, %29, %30, %31, %32, %33, %34, %35, %36, %37, %38, %39, %40, %41, %42, %43, %44, %45, %46, %47, %48, %49, %50, %51, %52, %53, %54, %55}, a, b, p1, 1, 1, 1, 0;\n"
      "add.s64 a, %56, 768;\n"
      "add.s64 b, %57, 900;\n"
      "wgmma.mma_async.sync.aligned.m64n112k16.f32.bf16.bf16 {%0, %1, %2, %3, %4, %5, %6, %7, %8, %9, %10, %11, %12, %13, %14, %15, %16, %17, %18, %19, %20, %21, %22, %23, %24, %25, %26, %27, %28, %29, %30, %31, %32, %33, %34, %35, %36, %37, %38, %39, %40, %41, %42, %43, %44, %45, %46, %47, %48, %49, %50, %51, %52, %53, %54, %55}, a, b, p1, 1, 1, 1, 0;\n"
      "add.s64 a, %56, 896;\n"
      "add.s64 b, %57, 902;\n"
      "wgmma.mma_async.sync.aligned.m64n112k16.f32.bf16.bf16 {%0, %1, %2, %3, %4, %5, %6, %7, %8, %9, %10, %11, %12, %13, %14, %15, %16, %17, %18, %19, %20, %21, %22, %23, %24, %25, %26, %27, %28, %29, %30, %31, %32, %33, %34, %35, %36, %37, %38, %39, %40, %41, %42, %43, %44, %45, %46, %47, %48, %49, %50, %51, %52, %53, %54, %55}, a, b, p1, 1, 1, 1, 0;\n"
      "}\n"
      : "=f"(A[0]), "=f"(A[1]), "=f"(A[2]), "=f"(A[3]), "=f"(A[4]), "=f"(A[5]), "=f"(A[6]), "=f"(A[7]),
        "=f"(A[8]), "=f"(A[9]), "=f"(A[10]), "=f"(A[11]), "=f"(A[12]), "=f"(A[13]), "=f"(A[14]), "=f"(A[15]),
        "=f"(A[16]), "=f"(A[17]), "=f"(A[18]), "=f"(A[19]), "=f"(A[20]), "=f"(A[21]), "=f"(A[22]), "=f"(A[23]),
        "=f"(A[24]), "=f"(A[25]), "=f"(A[26]), "=f"(A[27]), "=f"(A[28]), "=f"(A[29]), "=f"(A[30]), "=f"(A[31]),
        "=f"(A[32]), "=f"(A[33]), "=f"(A[34]), "=f"(A[35]), "=f"(A[36]), "=f"(A[37]), "=f"(A[38]), "=f"(A[39]),
        "=f"(A[40]), "=f"(A[41]), "=f"(A[42]), "=f"(A[43]), "=f"(A[44]), "=f"(A[45]), "=f"(A[46]), "=f"(A[47]),
        "=f"(A[48]), "=f"(A[49]), "=f"(A[50]), "=f"(A[51]), "=f"(A[52]), "=f"(A[53]), "=f"(A[54]), "=f"(A[55])
      : "l"(da), "l"(db));
}

__device__ __forceinline__ void issue_oproj(float (&A)[56], uint64_t da, uint64_t db) {
  asm volatile(
      "{\n"
      ".reg .b64 a, b;\n"
      ".reg .pred p0, p1;\n"
      "setp.ne.b32 p0, 0, 0;\n"
      "setp.eq.b32 p1, 0, 0;\n"
      "add.s64 a, %56, 0;\n"
      "add.s64 b, %57, 0;\n"
      "wgmma.mma_async.sync.aligned.m64n112k16.f32.bf16.bf16 {%0, %1, %2, %3, %4, %5, %6, %7, %8, %9, %10, %11, %12, %13, %14, %15, %16, %17, %18, %19, %20, %21, %22, %23, %24, %25, %26, %27, %28, %29, %30, %31, %32, %33, %34, %35, %36, %37, %38, %39, %40, %41, %42, %43, %44, %45, %46, %47, %48, %49, %50, %51, %52, %53, %54, %55}, a, b, p1, 1, 1, 1, 0;\n"
      "add.s64 a, %56, 128;\n"
      "add.s64 b, %57, 2;\n"
      "wgmma.mma_async.sync.aligned.m64n112k16.f32.bf16.bf16 {%0, %1, %2, %3, %4, %5, %6, %7, %8, %9, %10, %11, %12, %13, %14, %15, %16, %17, %18, %19, %20, %21, %22, %23, %24, %25, %26, %27, %28, %29, %30, %31, %32, %33, %34, %35, %36, %37, %38, %39, %40, %41, %42, %43, %44, %45, %46, %47, %48, %49, %50, %51, %52, %53, %54, %55}, a, b, p1, 1, 1, 1, 0;\n"
      "add.s64 a, %56, 256;\n"
      "add.s64 b, %57, 4;\n"
      "wgmma.mma_async.sync.aligned.m64n112k16.f32.bf16.bf16 {%0, %1, %2, %3, %4, %5, %6, %7, %8, %9, %10, %11, %12, %13, %14, %15, %16, %17, %18, %19, %20, %21, %22, %23, %24, %25, %26, %27, %28, %29, %30, %31, %32, %33, %34, %35, %36, %37, %38, %39, %40, %41, %42, %43, %44, %45, %46, %47, %48, %49, %50, %51, %52, %53, %54, %55}, a, b, p1, 1, 1, 1, 0;\n"
      "add.s64 a, %56, 384;\n"
      "add.s64 b, %57, 6;\n"
      "wgmma.mma_async.sync.aligned.m64n112k16.f32.bf16.bf16 {%0, %1, %2, %3, %4, %5, %6, %7, %8, %9, %10, %11, %12, %13, %14, %15, %16, %17, %18, %19, %20, %21, %22, %23, %24, %25, %26, %27, %28, %29, %30, %31, %32, %33, %34, %35, %36, %37, %38, %39, %40, %41, %42, %43, %44, %45, %46, %47, %48, %49, %50, %51, %52, %53, %54, %55}, a, b, p1, 1, 1, 1, 0;\n"
      "add.s64 a, %56, 512;\n"
      "add.s64 b, %57, 896;\n"
      "wgmma.mma_async.sync.aligned.m64n112k16.f32.bf16.bf16 {%0, %1, %2, %3, %4, %5, %6, %7, %8, %9, %10, %11, %12, %13, %14, %15, %16, %17, %18, %19, %20, %21, %22, %23, %24, %25, %26, %27, %28, %29, %30, %31, %32, %33, %34, %35, %36, %37, %38, %39, %40, %41, %42, %43, %44, %45, %46, %47, %48, %49, %50, %51, %52, %53, %54, %55}, a, b, p1, 1, 1, 1, 0;\n"
      "add.s64 a, %56, 640;\n"
      "add.s64 b, %57, 898;\n"
      "wgmma.mma_async.sync.aligned.m64n112k16.f32.bf16.bf16 {%0, %1, %2, %3, %4, %5, %6, %7, %8, %9, %10, %11, %12, %13, %14, %15, %16, %17, %18, %19, %20, %21, %22, %23, %24, %25, %26, %27, %28, %29, %30, %31, %32, %33, %34, %35, %36, %37, %38, %39, %40, %41, %42, %43, %44, %45, %46, %47, %48, %49, %50, %51, %52, %53, %54, %55}, a, b, p1, 1, 1, 1, 0;\n"
      "add.s64 a, %56, 768;\n"
      "add.s64 b, %57, 900;\n"
      "wgmma.mma_async.sync.aligned.m64n112k16.f32.bf16.bf16 {%0, %1, %2, %3, %4, %5, %6, %7, %8, %9, %10, %11, %12, %13, %14, %15, %16, %17, %18, %19, %20, %21, %22, %23, %24, %25, %26, %27, %28, %29, %30, %31, %32, %33, %34, %35, %36, %37, %38, %39, %40, %41, %42, %43, %44, %45, %46, %47, %48, %49, %50, %51, %52, %53, %54, %55}, a, b, p1, 1, 1, 1, 0;\n"
      "add.s64 a, %56, 896;\n"
      "add.s64 b, %57, 902;\n"
      "wgmma.mma_async.sync.aligned.m64n112k16.f32.bf16.bf16 {%0, %1, %2, %3, %4, %5, %6, %7, %8, %9, %10, %11, %12, %13, %14, %15, %16, %17, %18, %19, %20, %21, %22, %23, %24, %25, %26, %27, %28, %29, %30, %31, %32, %33, %34, %35, %36, %37, %38, %39, %40, %41, %42, %43, %44, %45, %46, %47, %48, %49, %50, %51, %52, %53, %54, %55}, a, b, p1, 1, 1, 1, 0;\n"
      "}\n"
      : "+f"(A[0]), "+f"(A[1]), "+f"(A[2]), "+f"(A[3]), "+f"(A[4]), "+f"(A[5]), "+f"(A[6]), "+f"(A[7]),
        "+f"(A[8]), "+f"(A[9]), "+f"(A[10]), "+f"(A[11]), "+f"(A[12]), "+f"(A[13]), "+f"(A[14]), "+f"(A[15]),
        "+f"(A[16]), "+f"(A[17]), "+f"(A[18]), "+f"(A[19]), "+f"(A[20]), "+f"(A[21]), "+f"(A[22]), "+f"(A[23]),
        "+f"(A[24]), "+f"(A[25]), "+f"(A[26]), "+f"(A[27]), "+f"(A[28]), "+f"(A[29]), "+f"(A[30]), "+f"(A[31]),
        "+f"(A[32]), "+f"(A[33]), "+f"(A[34]), "+f"(A[35]), "+f"(A[36]), "+f"(A[37]), "+f"(A[38]), "+f"(A[39]),
        "+f"(A[40]), "+f"(A[41]), "+f"(A[42]), "+f"(A[43]), "+f"(A[44]), "+f"(A[45]), "+f"(A[46]), "+f"(A[47]),
        "+f"(A[48]), "+f"(A[49]), "+f"(A[50]), "+f"(A[51]), "+f"(A[52]), "+f"(A[53]), "+f"(A[54]), "+f"(A[55])
      : "l"(da), "l"(db));
}

constexpr float kScale = 0.08838834764831845f * 1.4426950408889634f;

__device__ __forceinline__ void pack_tile(const float (&acc)[56], uint32_t (&p)[28], float scale) {
#pragma unroll
  for (int i = 0; i < 28; i++) p[i] = pack2(acc[2 * i] * scale, acc[2 * i + 1] * scale);
}
__device__ __forceinline__ void pack_tile(const float (&acc)[56], uint32_t (&p)[28]) {
#pragma unroll
  for (int i = 0; i < 28; i++) p[i] = pack2(acc[2 * i], acc[2 * i + 1]);
}
__device__ __forceinline__ void store_transposed(const uint32_t (&p)[28], uint32_t base, int warp, int lane) {
  const uint32_t a0 = base + ((lane >> 4) * 8 + (lane & 7)) * 128 + (((2 * warp + ((lane >> 3) & 1)) ^ (lane & 7)) << 4);
#pragma unroll
  for (int j = 0; j < 7; j++) stsm4t(a0 + j * 2048, p[4 * j], p[4 * j + 1], p[4 * j + 2], p[4 * j + 3]);
}

struct SoftmaxState {
  float m[2], l[2];
  uint32_t online;
};

template <bool HAS_O>
__device__ __forceinline__ void softmax_online(float (&S)[32], uint32_t (&P)[16], float* O, SoftmaxState& st) {
  float x0 = st.m[0], x1 = st.m[1];
#pragma unroll
  for (int j = 0; j < 8; j++) {
    x0 = fmaxf(x0, fmaxf(S[4 * j], S[4 * j + 1]));
    x1 = fmaxf(x1, fmaxf(S[4 * j + 2], S[4 * j + 3]));
  }
  x0 = fmaxf(x0, __shfl_xor_sync(0xffffffffu, x0, 1));
  x1 = fmaxf(x1, __shfl_xor_sync(0xffffffffu, x1, 1));
  x0 = fmaxf(x0, __shfl_xor_sync(0xffffffffu, x0, 2));
  x1 = fmaxf(x1, __shfl_xor_sync(0xffffffffu, x1, 2));
  const float a0 = ex2(st.m[0] - x0), a1 = ex2(st.m[1] - x1);
  float s0 = st.l[0] * a0, s1 = st.l[1] * a1;
  st.m[0] = x0;
  st.m[1] = x1;
#pragma unroll
  for (int j = 0; j < 8; j++) {
    const float p0 = ex2(S[4 * j] - x0), p1 = ex2(S[4 * j + 1] - x0);
    const float p2 = ex2(S[4 * j + 2] - x1), p3 = ex2(S[4 * j + 3] - x1);
    s0 += p0 + p1;
    s1 += p2 + p3;
    P[2 * j] = pack2(p0, p1);
    P[2 * j + 1] = pack2(p2, p3);
  }
  st.l[0] = s0;
  st.l[1] = s1;
#pragma unroll
  for (int i = 0; i < (HAS_O ? 16 : 0); i++) {
    O[4 * i] *= a0;
    O[4 * i + 1] *= a0;
    O[4 * i + 2] *= a1;
    O[4 * i + 3] *= a1;
  }
}

template <bool FLUSH>
__device__ __forceinline__ bool softmax_fast(float (&S)[32], uint32_t (&P)[16], SoftmaxState& st, const float* O, uint32_t row, int lane) {
  const float r0 = st.l[0], r1 = st.l[1];
  float s0 = FLUSH ? 0.f : st.l[0], s1 = FLUSH ? 0.f : st.l[1], t0 = 0.f, t1 = 0.f;
#pragma unroll
  for (int j = 0; j < 8; j++) {
    const float p0 = ex2(S[4 * j]), p1 = ex2(S[4 * j + 1]), p2 = ex2(S[4 * j + 2]), p3 = ex2(S[4 * j + 3]);
    s0 += p0;
    s1 += p2;
    if (j == 0) { t0 = p1; t1 = p3; } else { t0 += p1; t1 += p3; }
    P[2 * j] = pack2(p0, p1);
    P[2 * j + 1] = pack2(p2, p3);
    if (FLUSH)
      stsm4(row + (j >> 2) * SUB + (((((2 * j) & 7) + (lane >> 4)) ^ (lane & 7)) << 4), pack2(O[8 * j] * r0, O[8 * j + 1] * r0),
            pack2(O[8 * j + 2] * r1, O[8 * j + 3] * r1), pack2(O[8 * j + 4] * r0, O[8 * j + 5] * r0),
            pack2(O[8 * j + 6] * r1, O[8 * j + 7] * r1));
  }
  s0 += t0;
  s1 += t1;
  const uint32_t out_of_range = ((__float_as_uint(s0) - 0x2F800000u) | (__float_as_uint(s1) - 0x2F800000u)) & 0xE0000000u;
  const bool ok = __all_sync(0xffffffffu, out_of_range == 0);
  if (ok) {
    st.l[0] = s0;
    st.l[1] = s1;
  } else if (FLUSH) {
    st.l[0] = st.l[1] = 0.f;
  }
  return ok;
}
__device__ __forceinline__ void softmax_step(float (&S)[32], uint32_t (&P)[16], float (&O)[64], SoftmaxState& st, bool first,
                                             bool flush, uint32_t base, int lane) {
  if (flush || !st.online) {
    const uint32_t row = base + ((((lane >> 3) & 1) * 8 + (lane & 7)) << 7);
    st.online = 0;
    if (flush ? softmax_fast<true>(S, P, st, O, row, lane) : softmax_fast<false>(S, P, st, O, row, lane)) return;
    st.m[0] = st.m[1] = first ? -INFINITY : 0.f;
    st.online = 1;
  }
  softmax_online<true>(S, P, O, st);
}
__device__ __forceinline__ void softmax_first(float (&S)[32], uint32_t (&P)[16], SoftmaxState& st) {
  if (softmax_fast<false>(S, P, st, nullptr, 0, 0)) return;
  st.m[0] = st.m[1] = -INFINITY;
  st.online = 1;
  softmax_online<false>(S, P, nullptr, st);
}

__device__ __forceinline__ void finish_sums(float (&l)[2]) {
  float l0 = l[0], l1 = l[1];
  l0 += __shfl_xor_sync(0xffffffffu, l0, 1);
  l1 += __shfl_xor_sync(0xffffffffu, l1, 1);
  l0 += __shfl_xor_sync(0xffffffffu, l0, 2);
  l1 += __shfl_xor_sync(0xffffffffu, l1, 2);
  asm("rcp.approx.ftz.f32 %0, %1;" : "=f"(l[0]) : "f"(l0));
  asm("rcp.approx.ftz.f32 %0, %1;" : "=f"(l[1]) : "f"(l1));
}
__device__ __forceinline__ void store_o_half(int h, const float (&O)[64], uint32_t (&T)[16], const float (&r)[2], uint32_t base, int lane) {
  const uint32_t row = base + ((((lane >> 3) & 1) * 8 + (lane & 7)) << 7);
#pragma unroll
  for (int i = 0; i < 16; i++) T[i] = pack2(O[32 * h + 2 * i] * r[i & 1], O[32 * h + 2 * i + 1] * r[i & 1]);
  pin(T);
#pragma unroll
  for (int j = 0; j < 4; j++)
    stsm4(row + h * SUB + (((2 * j + (lane >> 4)) ^ (lane & 7)) << 4), T[4 * j], T[4 * j + 1], T[4 * j + 2], T[4 * j + 3]);
}
__device__ __forceinline__ void store_o(const float (&O)[64], uint32_t (&T)[16], const float (&r)[2], uint32_t base, int lane) {
  store_o_half(0, O, T, r, base, lane);
  store_o_half(1, O, T, r, base, lane);
}

constexpr int PF_TW = 3800;
constexpr int PF_T0 = 5000, PF_PACE = 1400, PF_N = 32;
constexpr int NEAR_T0 = 10500, NEAR_PACE = 1400, NEAR_N = 3;
constexpr int PF_TO = 51500;
constexpr int KV_GATE = 2, KV_GATE_END = 5;
constexpr int U_KV = 37, U_O = U_KV + 32;

__device__ __forceinline__ int out_tile(int t, int hp) {
  const int r = t + hp;
  return r >= 9 ? r - 9 : r;
}

__device__ __forceinline__ void sleep_until(long long t) {
  int wait;
  while ((wait = (int)(t - clock64())) > 0) __nanosleep(wait > 64 ? (unsigned)wait >> 1 : 32);
}

struct Params {
  CUtensorMap x, wq, k, v, wo, out;
  const uint8_t *px, *pk, *pv, *pwq, *pwo;
};

__global__ void __cluster_dims__(2, 1, 1) __launch_bounds__(384, 1)
gqa_fused_kernel(const __grid_constant__ Params prm, __nv_bfloat16* __restrict__ out, const uint32_t dhi, const int zero_here) {
  extern __shared__ __align__(1024) uint8_t smem_raw[];
  const long long t_entry = clock64();
  const uint32_t sb = (uint32_t)__cvta_generic_to_shared(smem_raw);
  const uint32_t bars = sb + BAR_OFF;
  const int cta = blockIdx.x;
  const int hp = cta >> 4;
  const int b = cta & 15;
  const int rank = cta & 1;

  if (threadIdx.x == 0) {
    mbar_init(bars + BAR_XFULL * 8, 1);
    mbar_init(bars + BAR_FULL * 8, 1);
    mbar_init(bars + (BAR_FULL + 1) * 8, 1);
    mbar_expect_tx(bars + BAR_FULL * 8, SLOT);
    tma3d(sb + RING_OFF, &prm.wq, bars + BAR_FULL * 8, 0, 0, hp * 8);
    mbar_expect_tx(bars + BAR_XFULL * 8, SUB);
    tma2d(sb, &prm.x, bars + BAR_XFULL * 8, 0, b * kSq);
    mbar_expect_tx(bars + (BAR_FULL + 1) * 8, SLOT);
    tma3d(sb + RING_OFF + SLOT, &prm.wq, bars + (BAR_FULL + 1) * 8, 0, 0, hp * 8 + 2);
  }
  __syncwarp();
  const int wg = __shfl_sync(0xffffffffu, (int)(threadIdx.x >> 7), 0);
  const int warp = __shfl_sync(0xffffffffu, (int)((threadIdx.x >> 5) & 3), 0);
  const int lane = threadIdx.x & 31;

  if (wg == 2) {
    asm volatile("setmaxnreg.dec.sync.aligned.u32 40;");
    cluster_arrive();
    cluster_wait();
    if (warp == 0) {
      if (lane == 0) {
        uint32_t slot = 0, ph = 0;
        const uint64_t stream_pol = stream_policy();
        auto acquire = [&]() -> uint32_t {
          mbar_wait(bars + (BAR_EMPTY + slot) * 8, ph);
          mbar_expect_tx(bars + (BAR_FULL + slot) * 8, SLOT);
          return slot;
        };
        auto advance = [&]() {
          if (++slot == NSLOT) { slot = 0; ph ^= 1; }
        };
        const int row0 = (b * kHkv + 2 * hp) * kSk;
#pragma unroll 1
        for (int u = 7; u < U_KV; u++) {
          const int v = u < 30 ? u - 2 : u < 33 ? 2 * u - 34 : u - 1;
          const int kb = v < 32 ? (int)(0x5546312887654321ull >> (((v >> 2) * 2 + (v & 1)) * 4)) & 15 : (v & 1) ? 0 : 7;
          if ((v < 16 && !(v & 2)) || u == 35) {
            const int xs = u == 35 ? 6 : kb & 7;
            if (xs != kb) mbar_wait(bars + BAR_XFREE * 8, u == 35);
            mbar_expect_tx(bars + (BAR_XFULL + xs) * 8, SUB);
            tma2d(sb + xs * SUB, &prm.x, bars + (BAR_XFULL + xs) * 8, u == 35 ? 0 : kb * 64, b * kSq);
          }
          const uint32_t s = acquire();
          if (u == 30) tma3d(sb + RING_OFF + s * SLOT, &prm.k, bars + (BAR_FULL + s) * 8, 0, row0, 0);
          else if (((v >> 1) & 1) == rank)
            tma3d_mc(sb + RING_OFF + s * SLOT, &prm.wq, bars + (BAR_FULL + s) * 8, 0, kb * 64, (hp * 4 + (v >= 16) * 2 + rank) * 2);
          advance();
          if (u == 9) {
            prefetch_map(&prm.k);
            prefetch_map(&prm.v);
          }

        }
#pragma unroll 1
        for (int c = 0; c < 32; c++) {
          const uint32_t s = acquire();
          if (c >= KV_GATE && c < KV_GATE_END) mbar_wait(bars + (BAR_FULL + (U_KV + c - KV_GATE) % NSLOT) * 8, ((U_KV + c - KV_GATE) / NSLOT) & 1);
          tma3d_hint(sb + RING_OFF + s * SLOT, (c & 1) ? &prm.v : &prm.k, bars + (BAR_FULL + s) * 8, 0, row0 + (c >> 1) * 64, 0, stream_pol);
          advance();
          if (c == 16) prefetch_map(&prm.wo);
        }
        prefetch_map(&prm.out);
#pragma unroll 1
        for (int t = 0; t < 9; t++) {
#pragma unroll 1
          for (int i = 0; i < 4; i++) {
            if (i != 2 || t < 2) {
              mbar_wait(bars + (BAR_EMPTY + slot) * 8, ph);
              if (i == 3) mbar_arrive(bars + (BAR_EMPTY + slot) * 8, 16);
              mbar_expect_tx(bars + (BAR_FULL + slot) * 8, SLOT);
              const uint32_t s = slot;
              if (((i ^ (t & (i >> 1))) & 1) == rank)
                tma2d_mc(sb + RING_OFF + s * SLOT, &prm.wo, bars + (BAR_FULL + s) * 8, out_tile(t, hp) * 64, (hp * 4 + (i ^ (i >> 1))) * 128);
            }
            advance();
          }
        }
        mbar_arrive(bars + BAR_DONE * 8, 1);
      }
    } else if (warp == 1) {
      if (zero_here) {
        __nanosleep(8000);
        uint4* dst = reinterpret_cast<uint4*>(out + ((size_t)b * kSq + hp * 14) * kD);
        for (int i = lane; i < 14 * kD * 2 / 16; i += 32) dst[i] = make_uint4(0, 0, 0, 0);
        __threadfence();
        __syncwarp();
      }
      if (lane == 0) {
        if (zero_here) {
          const unsigned old = atomicAdd(&g_zero_cnt[b], 1u);
          const unsigned target = (old / 8u + 1u) * 8u;
          unsigned cur;
          do {
            asm volatile("ld.acquire.gpu.global.u32 %0, [%1];" : "=r"(cur) : "l"(&g_zero_cnt[b]) : "memory");
            if ((int)(cur - target) < 0) __nanosleep(200);
          } while ((int)(cur - target) < 0);
        }
        asm volatile("fence.proxy.async.global;" ::: "memory");
        uint32_t slot = (U_O + 3) % NSLOT;
#pragma unroll 1
        for (int t = 0; t < 9; t++) {
          mbar_wait(bars + (BAR_STAGE + (t & 1)) * 8, (t >> 1) & 1);
          asm volatile("cp.reduce.async.bulk.tensor.2d.global.shared::cta.add.tile.bulk_group [%0, {%2, %3}], [%1];"
                       ::"l"(&prm.out), "r"(sb + RING_OFF + slot * SLOT), "r"(out_tile(t, hp) * 64), "r"(b * kSq) : "memory");
          asm volatile("cp.async.bulk.commit_group;" ::: "memory");
          asm volatile("cp.async.bulk.wait_group.read 0;" ::: "memory");
          if (t < 7) {
            mbar_expect_tx(bars + (BAR_FULL + slot) * 8, SLOT);
            tma2d(sb + RING_OFF + slot * SLOT, &prm.wo, bars + (BAR_FULL + slot) * 8, out_tile(t + 2, hp) * 64, (hp * 4 + 3) * 128);
          }
          slot += 4;
          if (slot >= NSLOT) slot -= NSLOT;
        }
        mbar_arrive(bars + BAR_DONE * 8, 1);
      }
    } else if (warp == 2) {
      const uint8_t* wq0 = prm.pwq + (size_t)((lane >> 2) * 16 + b) * 8192 + hp * 1024 + (lane & 3) * 128;
#pragma unroll
      for (int i = 0; i < 3; i++) l2_prefetch_line(wq0 + (size_t)(192 + i * 128) * 8192);
#pragma unroll
      for (int i = 0; i < 3; i++) {
        const int l = i * 32 + lane;
        if (l < 70) l2_prefetch_line(prm.px + ((size_t)b * kSq + hp * 14 + l % 14) * (kD * 2) + 512 + (l / 14) * 128);
      }
      sleep_until(t_entry + PF_TW);
#pragma unroll
      for (int i = 0; i < 5; i++)
        if (i < 4 || lane < 16) l2_prefetch_line(wq0 + (size_t)i * 128 * 8192 + 512);
      const uint64_t stream_pol = stream_policy();
      const size_t kv0 = (size_t)(b * kHkv + 2 * hp) * kSk * kDh * 2;
#pragma unroll 1
      for (int i = 0; i < PF_N * 2; i++) {
        const int c = i >> 1;
        sleep_until(t_entry + PF_T0 + i * (PF_PACE / 2));
        const uint8_t* p = ((c & 1) ? prm.pv : prm.pk) + kv0 + (size_t)(c >> 1) * SLOT + (i & 1) * (SLOT / 2);
        if (lane == 0) l2_prefetch_bulk(p, SLOT / 2, stream_pol);
      }
      sleep_until(t_entry + PF_TO);
#pragma unroll
      for (int i = 0; i < 9; i++) l2_prefetch_line(prm.pwo + ((size_t)hp * 512 + b * 32) * (kD * 2) + (i * 32 + lane) * 128);
    } else {
      if (lane == 0) {
        if (sb & 1023u) __trap();
        const size_t kv0 = (size_t)(b * kHkv + 2 * hp) * kSk * kDh * 2;
#pragma unroll 1
        for (int c = 1; c < 1 + NEAR_N; c++) {
          sleep_until(t_entry + NEAR_T0 + (c - 1) * NEAR_PACE);
          const uint8_t* p = ((c & 1) ? prm.pv : prm.pk) + kv0 + (size_t)(c >> 1) * SLOT;
          mbar_expect_tx(bars + BAR_SINK * 8, SLOT);
#pragma unroll 1
          for (int i = 0; i < SLOT / SINK; i++)
            asm volatile("cp.async.bulk.shared::cluster.global.mbarrier::complete_tx::bytes [%0], [%1], %2, [%3];"
                         ::"r"(sb + SINK_OFF), "l"(p + i * SINK), "r"(SINK), "r"(bars + BAR_SINK * 8) : "memory");
          mbar_wait(bars + BAR_SINK * 8, (c - 1) & 1);
        }
        unsigned long long t0, t1;
        asm volatile("mov.u64 %0, %%globaltimer;" : "=l"(t0));
        while (!mbar_try(bars + BAR_DONE * 8, 0)) {
          asm volatile("mov.u64 %0, %%globaltimer;" : "=l"(t1));
          if (t1 - t0 > 2000000000ull) __trap();
        }
      }
    }
  } else {
    if (threadIdx.x == 0) {
#pragma unroll
      for (int i = 0; i < NSLOT; i++) {
        if (i >= 2) mbar_init(bars + (BAR_FULL + i) * 8, 1);
        mbar_init(bars + (BAR_EMPTY + i) * 8, 16);
      }
#pragma unroll
      for (int i = 1; i < 8; i++) mbar_init(bars + (BAR_XFULL + i) * 8, 1);
      mbar_init(bars + BAR_XFREE * 8, 8);
      mbar_init(bars + BAR_STAGE * 8, 4);
      mbar_init(bars + (BAR_STAGE + 1) * 8, 4);
      mbar_init(bars + BAR_DONE * 8, 10);
      mbar_init(bars + BAR_SINK * 8, 1);
      asm volatile("fence.mbarrier_init.release.cluster;" ::: "memory");
    }
    __syncwarp();
    cluster_arrive();
    if (threadIdx.x == 0) {
#pragma unroll
      for (int kb = 1; kb < 3; kb++) {
        mbar_expect_tx(bars + (BAR_XFULL + kb) * 8, SUB);
        tma2d(sb + kb * SUB, &prm.x, bars + (BAR_XFULL + kb) * 8, kb * 64, b * kSq);
      }
#pragma unroll
      for (int s = 2; s < 7; s++) mbar_expect_tx(bars + (BAR_FULL + s) * 8, SLOT);
      mbar_expect_tx(bars + (BAR_XFULL + 3) * 8, SUB);
    }
    __syncwarp();
    cluster_wait();
    if (threadIdx.x == 0) {
      tma3d_mc(sb + RING_OFF + (2 + rank) * SLOT, &prm.wq, bars + (BAR_FULL + 2 + rank) * 8, 0, (1 + rank) * 64, hp * 8);
      tma3d_mc(sb + RING_OFF + (4 + rank) * SLOT, &prm.wq, bars + (BAR_FULL + 4 + rank) * 8, 0, (1 + rank) * 64, hp * 8 + 2);
      tma2d(sb + 3 * SUB, &prm.x, bars + (BAR_XFULL + 3) * 8, 3 * 64, b * kSq);
      if (rank == 0) tma3d_mc(sb + RING_OFF + 6 * SLOT, &prm.wq, bars + (BAR_FULL + 6) * 8, 0, 3 * 64, hp * 8);
    }
    __syncwarp();
    asm volatile("setmaxnreg.inc.sync.aligned.u32 232;");
    const int my_turn = 1 + wg, other_turn = 2 - wg, wg_bar = 3 + wg;
    uint32_t cs = wg * 8, cp = 0;
    auto step1 = [&]() { cs += 8; if (cs == 8 * NSLOT) { cs = 0; cp ^= 1; } };
    auto stepn = [&](uint32_t n) { cs += 8 * n; if (cs >= 8 * NSLOT) { cs -= 8 * NSLOT; cp ^= 1; } };
    auto wait_full = [&]() -> uint32_t {
      mbar_wait(bars + BAR_FULL * 8 + cs, cp);
      return cs;
    };
    auto slot_addr = [&](uint32_t s8) -> uint32_t { return sb + RING_OFF + s8 * (SLOT / 8); };
    const uint32_t empty_pair = mapa(bars + BAR_EMPTY * 8, rank ^ (lane & 1));
    auto release = [&](uint32_t s8, uint32_t cnt) {
      if (lane < 2) mbar_arrive_cluster(empty_pair + s8, cnt);
    };
    if (wg == 1) bar_arrive(1, 256);

    float OA[64], OB[64], S[32];
    uint32_t PA[16], PB[16];
    SoftmaxState sa = {{0.f, 0.f}, {0.f, 0.f}, 0u}, sbt = {{0.f, 0.f}, {0.f, 0.f}, 0u};
    uint32_t qa = sb + 2 * wg * SUB;
    uint32_t ks, vs, vprev = 0;
    uint64_t dk, dv;
    {
      float acc0[56], acc1[56];
      uint32_t q0[28], q1[28];
      auto xdesc = [&](int kb) -> uint64_t { return desc(sb + kb * SUB, 16, dhi); };
      auto free_x = [&]() {
        if (lane == 0) mbar_arrive(bars + BAR_XFREE * 8, 1);
      };
      auto pair = [&](auto store, int xa, int xb, int accumulate, uint32_t skip) {
        const uint32_t s0 = wait_full();
        step1();
        const uint32_t s1 = wait_full();
        stepn(skip);
        bar_sync(my_turn, 256);
        wg_fence();
        issue_qproj_acc(acc0, acc1, desc(slot_addr(s0), 8192, dhi), xdesc(xa), accumulate);
        wg_commit();
        issue_qproj(acc0, acc1, desc(slot_addr(s1), 8192, dhi), xdesc(xb));
        wg_commit();
        bar_arrive(other_turn, 256);
        wg_wait<1>();
        release(s0, 2);
        if (decltype(store)::value == 3) {
          if (wg == 0) bar_sync(8, 256);
          else bar_arrive(9, 256);
          store_transposed(q0, qa, warp, lane);
        }
        if (decltype(store)::value == 1) {
          free_x();
          if (wg == 0) bar_sync(9, 256);
          store_transposed(q1, qa + SUB, warp, lane);
        }
        wg_wait<0>();
        pin(acc0);
        pin(acc1);
        release(s1, 2);
        if (decltype(store)::value == 1) fence_async_smem();
      };
      {
        mbar_wait(bars + BAR_XFULL * 8, 0);
        const uint32_t s0 = wait_full();
        stepn(2 + wg);
        bar_sync(my_turn, 256);
        wg_fence();
        issue_qproj_first(acc0, acc1, desc(slot_addr(s0), 8192, dhi), xdesc(0));
        wg_commit();
        bar_arrive(other_turn, 256);
        wg_wait<0>();
        pin(acc0);
        pin(acc1);
        release(s0, 2);
        free_x();
      }
      zero(q0);
      zero(q1);
#pragma unroll 1
      for (int p = 0; p < 5; p++) {
        const int xa = p < 4 ? 2 * p + 1 : 0, xb = (2 * p + 2) & 7;
        if (p < 4) {
          mbar_wait(bars + (BAR_XFULL + xa) * 8, 0);
          mbar_wait(bars + (BAR_XFULL + xb) * 8, p == 3);
        }
        pair(std::integral_constant<int, 0>{}, xa, xb, p != 4, 3);
        if (p == 3) {
          pack_tile(acc0, q0, kScale);
          pack_tile(acc1, q1, kScale);
        }
      }
      if (wg == 1) bar_arrive(8, 256);
      pair(std::integral_constant<int, 3>{}, 1, 3, 1, 3);
      pair(std::integral_constant<int, 1>{}, 6, 4, 1, 3 - 2 * wg);
      {
        ks = wait_full();
        stepn(1 + wg);
        dk = desc(slot_addr(ks), 16, dhi);
        const uint32_t s0 = wait_full();
        stepn(2 + wg);
        bar_sync(my_turn, 256);
        wg_fence();
        issue_qk(S, desc(qa, 16, dhi), dk);
        wg_commit();
        issue_qproj(acc0, acc1, desc(slot_addr(s0), 8192, dhi), xdesc(5));
        wg_commit();
        bar_arrive(other_turn, 256);
        wg_wait<1>();
        pin(S);
        release(ks, 1);
        softmax_first(S, PA, sa);
        wg_wait<0>();
        pin(acc0);
        pin(acc1);
        release(s0, 2);
        if (wg == 1) bar_arrive(7, 256);
      }
      mbar_wait(bars + (BAR_XFULL + 6) * 8, 1);
      pair(std::integral_constant<int, 0>{}, 7, 6, 1, 3 - 2 * wg);
      ks = cs;
      const uint32_t kp = cp;
      step1();
      vs = cs;
      const uint32_t vp = cp;
      step1();
      const bool ready = mbar_test(bars + BAR_FULL * 8 + ks, kp) && mbar_test(bars + BAR_FULL * 8 + vs, vp);
      dk = desc(slot_addr(ks), 16, dhi);
      dv = desc(slot_addr(vs), 8192, dhi);
      if (wg == 0) bar_arrive(6, 256);
      bar_sync(7 - wg, 256);
      pack_tile(acc0, q0, kScale);
      store_transposed(q0, qa + QO, warp, lane);
      pack_tile(acc1, q1, kScale);
      store_transposed(q1, qa + QO + SUB, warp, lane);
      if (!__all_sync(0xffffffffu, ready)) {
        mbar_wait(bars + BAR_FULL * 8 + ks, kp);
        mbar_wait(bars + BAR_FULL * 8 + vs, vp);
      }
#pragma unroll
      for (int i = 0; i < 64; i++) {
        OA[i] = i < 56 ? acc0[i] : 0.f;
        OB[i] = i < 56 ? acc1[i] : 0.f;
      }
#pragma unroll
      for (int i = 0; i < 16; i++) PB[i] = 0;
    }
    auto step_b = [&](int j, bool last) {
      wg_wait<0>();
      pin(OB);
      pin(PB);
      pin(PA);
      pin(OA);
      if (j > 0) release(vprev, 1);
      bar_sync(my_turn, 256);
      wg_fence();
      issue_qk(S, desc(qa + 8192, 16, dhi), dk);
      wg_commit();
      issue_pv(OA, PA, dv, j & 7);
      wg_commit();
      bar_arrive(other_turn, 256);
      const uint32_t kprev = ks, np = cp;
      bool ready = true;
      if (!last) {
        ks = cs;
        ready = mbar_test(bars + BAR_FULL * 8 + ks, np);
        step1();
        dk = desc(slot_addr(ks), 16, dhi);
      }
      wg_wait<1>();
      pin(S);
      release(kprev, 1);
      if (warp < 3)
        softmax_step(S, PB, OB, sbt, (j & 7) == 0, !last && j == 8, qa - QO + 8192 + warp * 2048, lane);
      if ((j & 7) == 7) finish_sums(sa.l);
      if (!__all_sync(0xffffffffu, ready)) mbar_wait(bars + BAR_FULL * 8 + ks, np);
    };
#pragma unroll 1
    for (int j = 0; j < 15; j++) {
      step_b(j, false);
      wg_wait<0>();
      pin(OA);
      pin(PA);
      pin(PB);
      pin(OB);
      if (j == 7) qa += QO;
      bar_sync(my_turn, 256);
      wg_fence();
      issue_qk(S, desc(qa, 16, dhi), dk);
      wg_commit();
      issue_pv(OB, PB, dv, j & 7);
      wg_commit();
      bar_arrive(other_turn, 256);
      vprev = vs;
      vs = cs;
      const uint32_t np = cp;
      const bool ready = mbar_test(bars + BAR_FULL * 8 + vs, np);
      step1();
      dv = desc(slot_addr(vs), 8192, dhi);
      if ((j & 7) == 1) fence_async_smem();
      if (j == 7) finish_sums(sbt.l);
      wg_wait<1>();
      pin(S);
      softmax_step(S, PA, OA, sa, j == 7, j == 7, qa - QO + warp * 2048, lane);
      if (!__all_sync(0xffffffffu, ready)) mbar_wait(bars + BAR_FULL * 8 + vs, np);
    }
    step_b(15, true);
    wg_wait<0>();
    pin(OA);
    pin(PA);
    pin(PB);
    pin(OB);
    bar_sync(my_turn, 256);
    wg_fence();
    issue_pv(OB, PB, dv, 1);
    wg_commit();
    bar_arrive(other_turn, 256);
    if (wg == 0) {
      mbar_wait(bars + BAR_FULL * 8 + cs, cp);
      mbar_wait(bars + BAR_FULL * 8 + (cs + 8 == 8 * NSLOT ? 0 : cs + 8), cs + 8 == 8 * NSLOT ? cp ^ 1 : cp);
    }
    finish_sums(sbt.l);
    store_o(OA, PA, sa.l, qa + warp * 2048, lane);
    wg_wait<0>();
    pin(OB);
    pin(PB);
    release(vs, 1);
    if (warp < 3) store_o(OB, PB, sbt.l, qa + 8192 + warp * 2048, lane);
    if (wg == 1) fence_async_smem();
    {
      if (wg == 1) {
        stepn(4);
        bar_sync(5, 256);
      }
      auto issue_k = [&](float (&acc)[56], uint32_t s8, int i, bool first) {
        const uint64_t da = desc(slot_addr(s8), 8192, dhi), db = desc(sb + i * 2 * SUB, 16, dhi);
        if (first) issue_oproj_first(acc, da, db);
        else issue_oproj(acc, da, db);
        wg_commit();
      };
#pragma unroll 1
      for (int t = wg; t < 9; t += 2) {
        float acc[56];
        const uint32_t s0 = t == 0 ? cs : wait_full();
        step1();
        const uint32_t s1 = t == 0 ? cs : wait_full();
        step1();
        bar_sync(my_turn, 256);
        wg_fence();
        issue_k(acc, s0, 0, true);
        issue_k(acc, s1, 1, false);
        if (t == 0) {
          fence_async_smem();
          bar_sync(wg_bar, 128);
        }
        const uint32_t s2 = cs, p2 = cp;
        step1();
        const uint32_t s3 = wait_full();
        stepn(5);
        wg_wait<1>();
        if (t < 8) release(s0, 2);
        wg_fence();
        issue_k(acc, s3, 2, false);
        mbar_wait(bars + BAR_FULL * 8 + s2, p2);
        wg_wait<1>();
        if (t < 7) release(s1, 2);
        if (t == 0) bar_sync(5, 256);
        wg_fence();
        issue_k(acc, s2, 3, false);
        bar_arrive(other_turn, 256);
        wg_wait<1>();
        bar_sync(wg_bar, 128);
        wg_wait<0>();
        if (t < 7) release(s2, 2);
        pin(acc);
        uint32_t pk[28];
        pack_tile(acc, pk);
        store_transposed(pk, slot_addr(s3), warp, lane);
        fence_async_smem();
        __syncwarp();
        if (lane == 0) mbar_arrive(bars + (BAR_STAGE + wg) * 8, 1);
      }
    }
    if (lane == 0) mbar_arrive(bars + BAR_DONE * 8, 1);
  }
}

typedef CUresult (*EncodeFn)(CUtensorMap*, CUtensorMapDataType, cuuint32_t, void*, const cuuint64_t*, const cuuint64_t*,
                             const cuuint32_t*, const cuuint32_t*, CUtensorMapInterleave, CUtensorMapSwizzle,
                             CUtensorMapL2promotion, CUtensorMapFloatOOBfill);

void encode(EncodeFn fn, CUtensorMap* m, const void* p, int rank, const cuuint64_t* dims, const cuuint64_t* strides,
            const cuuint32_t* box) {
  cuuint32_t es[3] = {1, 1, 1};
  fn(m, CU_TENSOR_MAP_DATA_TYPE_BFLOAT16, rank, const_cast<void*>(p), dims, strides, box, es, CU_TENSOR_MAP_INTERLEAVE_NONE,
     CU_TENSOR_MAP_SWIZZLE_128B, CU_TENSOR_MAP_L2_PROMOTION_L2_128B, CU_TENSOR_MAP_FLOAT_OOB_FILL_NONE);
}

}

extern "C" void kernel_launch(void* const* d_in, const int* in_sizes, int n_in, void* d_out, int out_size) {
  cudaLaunchConfig_t cfg = {};
  cfg.gridDim = dim3(128);
  cfg.blockDim = dim3(384);
  cfg.dynamicSmemBytes = SMEM_BYTES;
  cfg.stream = cudaStreamPerThread;
  cudaLaunchAttribute at[1];
  at[0].id = cudaLaunchAttributeClusterDimension;
  at[0].val.clusterDim.x = 2;
  at[0].val.clusterDim.y = 1;
  at[0].val.clusterDim.z = 1;
  cfg.attrs = at;
  cfg.numAttrs = 1;

  static EncodeFn fn = nullptr;
  static int co_resident = 0;
  if (!fn) {
    void* p = nullptr;
    cudaDriverEntryPointQueryResult qr;
    cudaGetDriverEntryPoint("cuTensorMapEncodeTiled", &p, cudaEnableDefault, &qr);
    fn = (EncodeFn)p;
    cudaFuncSetAttribute(gqa_fused_kernel, cudaFuncAttributeMaxDynamicSharedMemorySize, SMEM_BYTES);
    int clusters = 0;
    co_resident = cudaOccupancyMaxActiveClusters(&clusters, gqa_fused_kernel, &cfg) == cudaSuccess && clusters >= 64;
  }
  Params prm;
  {
    cuuint64_t d[2] = {kD, (cuuint64_t)kB * kSq}, s[1] = {kD * 2};
    cuuint32_t bx[2] = {64, kSq};
    encode(fn, &prm.x, d_in[0], 2, d, s, bx);
    encode(fn, &prm.out, d_out, 2, d, s, bx);
  }
  {
    cuuint64_t d[3] = {64, (cuuint64_t)kB * kHkv * kSk, 2}, s[2] = {kDh * 2, 128};
    cuuint32_t bx[3] = {64, 64, 2};
    encode(fn, &prm.k, d_in[1], 3, d, s, bx);
    encode(fn, &prm.v, d_in[2], 3, d, s, bx);
  }
  {
    cuuint64_t d[3] = {64, kD, kHq * kDh / 64}, s[2] = {kHq * kDh * 2, 128};
    cuuint32_t bx[3] = {64, 64, 2};
    encode(fn, &prm.wq, d_in[3], 3, d, s, bx);
  }
  {
    cuuint64_t d[2] = {kD, kHq * kDh}, s[1] = {kD * 2};
    cuuint32_t bx[2] = {64, 128};
    encode(fn, &prm.wo, d_in[4], 2, d, s, bx);
  }
  prm.px = (const uint8_t*)d_in[0];
  prm.pwq = (const uint8_t*)d_in[3];
  prm.pk = (const uint8_t*)d_in[1];
  prm.pv = (const uint8_t*)d_in[2];
  prm.pwo = (const uint8_t*)d_in[4];
  if (!co_resident) cudaMemsetAsync(d_out, 0, (size_t)kB * kSq * kD * 2, cudaStreamPerThread);
  cudaLaunchKernelEx(&cfg, gqa_fused_kernel, prm, (__nv_bfloat16*)d_out, 0x40000040u, co_resident);
}
```
